```python
import torch

def _softmax(x, axis=-1):
    return torch.softmax(x, dim=axis)
def _gelu(x):
    return torch.nn.functional.gelu(x, approximate="tanh")
def _silu(x):
    return torch.nn.functional.silu(x)
def _sigmoid(x):
    return torch.sigmoid(x)
def _layernorm(x, axis=-1, eps=1e-5):
    m = x.mean(dim=axis, keepdim=True)
    v = x.var(dim=axis, keepdim=True, unbiased=False)
    return (x - m) / torch.sqrt(v + eps)
def _scatter_add(tgt, idx, src, axis=0):
    return tgt.clone().index_add_(axis, idx, src)
def _segment_sum(src, seg, n):
    out = torch.zeros((n,) + src.shape[1:], dtype=src.dtype)
    return out.index_add_(0, seg, src)
def _pad(x, pw):
    flat = tuple(v for pair in reversed(pw) for v in pair)
    return torch.nn.functional.pad(x, flat)

kernel_name = 'gated_mix__mha_block__sliding_local_dilated__prompt'

def setup_inputs():

    _w = (lambda a: (lambda t: t.to(torch.bfloat16) if t.is_floating_point() else t)(torch.as_tensor(a)))
    def _A_setup():
        B, S, D, H = 1, 2048, 576, 32
        return {
            "x": _w((lambda *s: torch.randn(*s, dtype=torch.bfloat16) * 0.05)(B, S, D)),
            "wqkv": _w((lambda *s: torch.randn(*s, dtype=torch.bfloat16) * 1.6)(D, 3 * D)),
            "wo": _w((lambda *s: torch.randn(*s, dtype=torch.bfloat16) * 0.1)(D, D)),
        }
    _A_in = _A_setup()

    def _B_setup():
        B, S, D = 1, 2048, 576
        return {
            "x": _w((lambda *s: torch.randn(*s, dtype=torch.bfloat16) * 0.05)(B, S, D)),
            "wqkv": _w((lambda *s: torch.randn(*s, dtype=torch.bfloat16) * 1.6)(D, 3 * D)),
            "wo": _w((lambda *s: torch.randn(*s, dtype=torch.bfloat16) * 0.05)(D, D)),
        }
    _B_in = _B_setup()

    return {
        "A_x": _A_in["x"],
        "A_wqkv": _A_in["wqkv"],
        "A_wo": _A_in["wo"],
        "B_x": _B_in["x"],
        "B_wqkv": _B_in["wqkv"],
        "B_wo": _B_in["wo"],
        "gate_w": _w((lambda *s: torch.randn(*s, dtype=torch.bfloat16) * 0.05)(576) * 16.0),
    }

def reference(A_x, A_wqkv, A_wo, B_x, B_wqkv, B_wo, gate_w):
    def _A_ref(x, wqkv, wo):
        B, S, D = x.shape
        H = 32
        Dh = D // H
        qkv = (lambda x, *d: x.permute(*d))((x @ wqkv).reshape(B, S, 3, H, Dh), 2, 0, 3, 1, 4)
        q, k, v = qkv[0], qkv[1], qkv[2]
        scores = torch.einsum("bhqd,bhkd->bhqk", q, k) * (Dh ** -0.5)
        p = _softmax(scores, axis=-1)
        o = torch.einsum("bhqk,bhkd->bhqd", p, v)
        return (lambda x, *d: x.permute(*d))(o, 0, 2, 1, 3).reshape(B, S, D) @ wo

    def _B_ref(x, wqkv, wo):
        B, S, D = x.shape
        H = 32; Dh = D // H
        W, dil = 8, 2
        qkv = (lambda x, *d: x.permute(*d))((x @ wqkv).reshape(B, S, 3, H, Dh), 2, 0, 3, 1, 4)
        q, k, v = qkv[0], qkv[1], qkv[2]
        scale = Dh ** -0.5
        pos = torch.arange(S)
        off = torch.arange(W) * dil
        idx = pos[:, None] - off[None, :]
        mask = idx >= 0
        idx_c = torch.where(mask, idx, 0).reshape(-1)
        kg = k[:, :, idx_c, :].reshape(B, H, S, W, Dh)
        vg = v[:, :, idx_c, :].reshape(B, H, S, W, Dh)
        logits = torch.einsum("bhsd,bhswd->bhsw", q, kg) * scale
        logits = torch.where(mask[None, None, :, :], logits, -1e9)
        attn = _softmax(logits, axis=-1)
        o = torch.einsum("bhsw,bhswd->bhsd", attn, vg)
        return (lambda x, *d: x.permute(*d))(o, 0, 2, 1, 3).reshape(B, S, D) @ wo

    x = A_x
    g = _sigmoid((x * gate_w).sum(-1, keepdims=True))
    a = _A_ref(x, A_wqkv, A_wo)
    b = _B_ref(x, B_wqkv, B_wo)
    return g * a + (1 - g) * b
```

```cpp
#include <cuda_runtime.h>
#include <cuda_bf16.h>
#include <cuda_fp16.h>
#include <cuda.h>
#include <stdint.h>


constexpr int SEQ = 2048, DM = 576;
constexpr int CB = SEQ * 16;
constexpr int CB_QA = 0, CB_KA = 72, CB_VA = 144, CB_B = 240, CB_OB = 456, CB_TOTAL = 528;
constexpr float QSCALE = 0.23570226039551584f * 1.4426950408889634f;
constexpr float QA_SCALE = -QSCALE / 4096.f, KA_SCALE = 1.f / 128.f;

__device__ __align__(1024) uint8_t g_scr[(size_t)CB_TOTAL * CB];
__device__ float g_gate[SEQ];
__device__ float4 g_part[128 * 2 * 3 * 128];
__device__ __align__(16) uint16_t g_kn[34 * SEQ];
__device__ unsigned g_cnt[4 * 32];

__device__ __forceinline__ uint32_t s2u(const void* p) { return (uint32_t)__cvta_generic_to_shared(p); }
__device__ __forceinline__ void mbar_init(uint32_t bar, int cnt) { asm volatile("mbarrier.init.shared::cta.b64 [%0], %1;" :: "r"(bar), "r"(cnt) : "memory"); }
__device__ __forceinline__ void mbar_expect(uint32_t bar, uint32_t bytes) { asm volatile("mbarrier.arrive.expect_tx.shared::cta.b64 _, [%0], %1;" :: "r"(bar), "r"(bytes) : "memory"); }
__device__ __forceinline__ void mbar_arrive(uint32_t bar) { asm volatile("mbarrier.arrive.shared::cta.b64 _, [%0];" :: "r"(bar) : "memory"); }
__device__ __forceinline__ void mbar_wait(uint32_t bar, uint32_t parity) {
    asm volatile("{\n.reg .pred p;\n.reg .u32 c;\n"
        "mbarrier.try_wait.parity.shared::cta.b64 p, [%0], %1;\n@p bra DONE_%=;\nmov.u32 c, 0;\n"
        "WAIT_%=:\nmbarrier.try_wait.parity.shared::cta.b64 p, [%0], %1;\n@p bra DONE_%=;\n"
        "add.u32 c, c, 1;\nsetp.lt.u32 p, c, 400000;\n@p bra WAIT_%=;\ntrap;\nDONE_%=:\n}" :: "r"(bar), "r"(parity) : "memory");
}
__device__ __forceinline__ void tma2d(uint32_t dst, const CUtensorMap* m, int c0, int c1, uint32_t bar) {
    asm volatile("cp.async.bulk.tensor.2d.shared::cluster.global.mbarrier::complete_tx::bytes [%0], [%1, {%3, %4}], [%2];"
        :: "r"(dst), "l"(m), "r"(bar), "r"(c0), "r"(c1) : "memory");
}
__device__ __forceinline__ void wg_fence() { asm volatile("wgmma.fence.sync.aligned;" ::: "memory"); }
__device__ __forceinline__ void wg_commit() { asm volatile("wgmma.commit_group.sync.aligned;" ::: "memory"); }
template<int N> __device__ __forceinline__ void wg_wait() { asm volatile("wgmma.wait_group.sync.aligned %0;" :: "n"(N) : "memory"); }
__device__ __forceinline__ uint64_t mkdesc(uint32_t addr, uint32_t lbo, uint32_t sbo, uint32_t swz) {
    return (uint64_t)((addr & 0x3FFFF) >> 4) | ((uint64_t)(lbo >> 4) << 16) | ((uint64_t)(sbo >> 4) << 32) | ((uint64_t)swz << 62);
}
template<int R> __device__ __forceinline__ void fence_regs(float (&d)[R]) {
    #pragma unroll
    for (int i = 0; i < R; i++) asm volatile("" : "+f"(d[i]) :: "memory");
}
template<int R> __device__ __forceinline__ void fence_regs(uint32_t (&d)[R]) {
    #pragma unroll
    for (int i = 0; i < R; i++) asm volatile("" : "+r"(d[i]) :: "memory");
}
__device__ __forceinline__ uint32_t pack_bf16(float lo, float hi) {
    uint32_t r; asm("cvt.rn.bf16x2.f32 %0, %1, %2;" : "=r"(r) : "f"(hi), "f"(lo)); return r;
}
__device__ __forceinline__ uint32_t pack_f16(float lo, float hi) {
    uint32_t r; asm("cvt.rn.f16x2.f32 %0, %1, %2;" : "=r"(r) : "f"(hi), "f"(lo)); return r;
}
__device__ __forceinline__ float bf_lo(uint32_t v) { return __uint_as_float(v << 16); }
__device__ __forceinline__ float bf_hi(uint32_t v) { return __uint_as_float(v & 0xffff0000u); }
__device__ __forceinline__ float ex2(float x) { float r; asm("ex2.approx.ftz.f32 %0, %1;" : "=f"(r) : "f"(x)); return r; }
__device__ __forceinline__ float rbf(float x) { return __bfloat162float(__float2bfloat16(x)); }
__device__ __forceinline__ void stg32(void* p, uint32_t v) { asm volatile("st.global.u32 [%0], %1;" :: "l"(p), "r"(v) : "memory"); }
__device__ __forceinline__ uint32_t ldg32(const void* p) { uint32_t v; asm volatile("ld.global.u32 %0, [%1];" : "=r"(v) : "l"(p) : "memory"); return v; }
__device__ __forceinline__ bool elect_one() {
    uint32_t p; asm volatile("{\n.reg .pred P;\nelect.sync _|P, 0xffffffff;\nselp.u32 %0, 1, 0, P;\n}" : "=r"(p)); return p;
}
__device__ __forceinline__ uint32_t uniform(uint32_t v) { asm volatile("" : "+r"(v)); return __shfl_sync(0xffffffffu, v, 0); }
__device__ __forceinline__ uint32_t lds32(uint32_t a) { uint32_t v; asm volatile("ld.shared.u32 %0, [%1];" : "=r"(v) : "r"(a) : "memory"); return v; }
__device__ __forceinline__ uint4 lds128(uint32_t a) { uint4 v; asm volatile("ld.shared.v4.u32 {%0,%1,%2,%3}, [%4];" : "=r"(v.x), "=r"(v.y), "=r"(v.z), "=r"(v.w) : "r"(a) : "memory"); return v; }
__device__ __forceinline__ void sts32(uint32_t a, uint32_t v) { asm volatile("st.shared.u32 [%0], %1;" :: "r"(a), "r"(v) : "memory"); }
template<int N> __device__ __forceinline__ void reg_inc() { asm volatile("setmaxnreg.inc.sync.aligned.u32 %0;" :: "n"(N)); }
template<int N> __device__ __forceinline__ void reg_dec() { asm volatile("setmaxnreg.dec.sync.aligned.u32 %0;" :: "n"(N)); }

__device__ __forceinline__ void wg_qk0(uint32_t (&d)[32], uint32_t a0, uint32_t a1, uint32_t a2, uint32_t a3, uint64_t db) {
    asm volatile("{\n.reg .pred p;\nsetp.ne.b32 p, 0, 0;\n"
        "wgmma.mma_async.sync.aligned.m64n128k16.f16.f16.f16 {%0, %1, %2, %3, %4, %5, %6, %7, %8, %9, %10, %11, %12, %13, %14, %15, %16, %17, %18, %19, %20, %21, %22, %23, %24, %25, %26, %27, %28, %29, %30, %31}, {%32, %33, %34, %35}, %36, p, 1, 1, 0;\n}\n"
        : "=r"(d[0]), "=r"(d[1]), "=r"(d[2]), "=r"(d[3]), "=r"(d[4]), "=r"(d[5]), "=r"(d[6]), "=r"(d[7]),
          "=r"(d[8]), "=r"(d[9]), "=r"(d[10]), "=r"(d[11]), "=r"(d[12]), "=r"(d[13]), "=r"(d[14]), "=r"(d[15]),
          "=r"(d[16]), "=r"(d[17]), "=r"(d[18]), "=r"(d[19]), "=r"(d[20]), "=r"(d[21]), "=r"(d[22]), "=r"(d[23]),
          "=r"(d[24]), "=r"(d[25]), "=r"(d[26]), "=r"(d[27]), "=r"(d[28]), "=r"(d[29]), "=r"(d[30]), "=r"(d[31])
        : "r"(a0), "r"(a1), "r"(a2), "r"(a3), "l"(db));
}
__device__ __forceinline__ void wg_qk1(uint32_t (&d)[32], uint32_t a0, uint32_t a1, uint32_t a2, uint32_t a3, uint64_t db) {
    asm volatile("{\n.reg .pred p;\nsetp.ne.b32 p, 1, 0;\n"
        "wgmma.mma_async.sync.aligned.m64n128k16.f16.f16.f16 {%0, %1, %2, %3, %4, %5, %6, %7, %8, %9, %10, %11, %12, %13, %14, %15, %16, %17, %18, %19, %20, %21, %22, %23, %24, %25, %26, %27, %28, %29, %30, %31}, {%32, %33, %34, %35}, %36, p, 1, 1, 0;\n}\n"
        : "+r"(d[0]), "+r"(d[1]), "+r"(d[2]), "+r"(d[3]), "+r"(d[4]), "+r"(d[5]), "+r"(d[6]), "+r"(d[7]),
          "+r"(d[8]), "+r"(d[9]), "+r"(d[10]), "+r"(d[11]), "+r"(d[12]), "+r"(d[13]), "+r"(d[14]), "+r"(d[15]),
          "+r"(d[16]), "+r"(d[17]), "+r"(d[18]), "+r"(d[19]), "+r"(d[20]), "+r"(d[21]), "+r"(d[22]), "+r"(d[23]),
          "+r"(d[24]), "+r"(d[25]), "+r"(d[26]), "+r"(d[27]), "+r"(d[28]), "+r"(d[29]), "+r"(d[30]), "+r"(d[31])
        : "r"(a0), "r"(a1), "r"(a2), "r"(a3), "l"(db));
}
__device__ __forceinline__ void wg_pv(float (&d)[12], uint32_t a0, uint32_t a1, uint32_t a2, uint32_t a3, uint64_t db) {
    asm volatile("{\n.reg .pred p;\nsetp.ne.b32 p, 1, 0;\n"
        "wgmma.mma_async.sync.aligned.m64n24k16.f32.bf16.bf16 {%0, %1, %2, %3, %4, %5, %6, %7, %8, %9, %10, %11}, {%12, %13, %14, %15}, %16, p, 1, 1, 1;\n}\n"
        : "+f"(d[0]), "+f"(d[1]), "+f"(d[2]), "+f"(d[3]), "+f"(d[4]), "+f"(d[5]), "+f"(d[6]), "+f"(d[7]),
          "+f"(d[8]), "+f"(d[9]), "+f"(d[10]), "+f"(d[11])
        : "r"(a0), "r"(a1), "r"(a2), "r"(a3), "l"(db));
}
__device__ __forceinline__ void wg_pv0(float (&d)[12], uint32_t a0, uint32_t a1, uint32_t a2, uint32_t a3, uint64_t db) {
    asm volatile("{\n.reg .pred p;\nsetp.ne.b32 p, 0, 0;\n"
        "wgmma.mma_async.sync.aligned.m64n24k16.f32.bf16.bf16 {%0, %1, %2, %3, %4, %5, %6, %7, %8, %9, %10, %11}, {%12, %13, %14, %15}, %16, p, 1, 1, 1;\n}\n"
        : "=f"(d[0]), "=f"(d[1]), "=f"(d[2]), "=f"(d[3]), "=f"(d[4]), "=f"(d[5]), "=f"(d[6]), "=f"(d[7]),
          "=f"(d[8]), "=f"(d[9]), "=f"(d[10]), "=f"(d[11])
        : "r"(a0), "r"(a1), "r"(a2), "r"(a3), "l"(db));
}
__device__ __forceinline__ void wg_g1h(float (&d)[64], uint64_t da, uint64_t db, int acc) {
    asm volatile("{\n.reg .pred p;\nsetp.ne.b32 p, %66, 0;\n"
        "wgmma.mma_async.sync.aligned.m64n128k16.f32.bf16.bf16 {%0, %1, %2, %3, %4, %5, %6, %7, %8, %9, %10, %11, %12, %13, %14, %15, %16, %17, %18, %19, %20, %21, %22, %23, %24, %25, %26, %27, %28, %29, %30, %31, %32, %33, %34, %35, %36, %37, %38, %39, %40, %41, %42, %43, %44, %45, %46, %47, %48, %49, %50, %51, %52, %53, %54, %55, %56, %57, %58, %59, %60, %61, %62, %63}, %64, %65, p, 1, 1, 0, 1;\n}\n"
        : "+f"(d[0]), "+f"(d[1]), "+f"(d[2]), "+f"(d[3]), "+f"(d[4]), "+f"(d[5]), "+f"(d[6]), "+f"(d[7]),
          "+f"(d[8]), "+f"(d[9]), "+f"(d[10]), "+f"(d[11]), "+f"(d[12]), "+f"(d[13]), "+f"(d[14]), "+f"(d[15]),
          "+f"(d[16]), "+f"(d[17]), "+f"(d[18]), "+f"(d[19]), "+f"(d[20]), "+f"(d[21]), "+f"(d[22]), "+f"(d[23]),
          "+f"(d[24]), "+f"(d[25]), "+f"(d[26]), "+f"(d[27]), "+f"(d[28]), "+f"(d[29]), "+f"(d[30]), "+f"(d[31]),
          "+f"(d[32]), "+f"(d[33]), "+f"(d[34]), "+f"(d[35]), "+f"(d[36]), "+f"(d[37]), "+f"(d[38]), "+f"(d[39]),
          "+f"(d[40]), "+f"(d[41]), "+f"(d[42]), "+f"(d[43]), "+f"(d[44]), "+f"(d[45]), "+f"(d[46]), "+f"(d[47]),
          "+f"(d[48]), "+f"(d[49]), "+f"(d[50]), "+f"(d[51]), "+f"(d[52]), "+f"(d[53]), "+f"(d[54]), "+f"(d[55]),
          "+f"(d[56]), "+f"(d[57]), "+f"(d[58]), "+f"(d[59]), "+f"(d[60]), "+f"(d[61]), "+f"(d[62]), "+f"(d[63])
        : "l"(da), "l"(db), "r"(acc));
}
__device__ __forceinline__ void wg_g1b(float (&d)[96], uint64_t da, uint64_t db, int acc) {
    asm volatile("{\n.reg .pred p;\nsetp.ne.b32 p, %98, 0;\n"
        "wgmma.mma_async.sync.aligned.m64n192k16.f32.bf16.bf16 {%0, %1, %2, %3, %4, %5, %6, %7, %8, %9, %10, %11, %12, %13, %14, %15, %16, %17, %18, %19, %20, %21, %22, %23, %24, %25, %26, %27, %28, %29, %30, %31, %32, %33, %34, %35, %36, %37, %38, %39, %40, %41, %42, %43, %44, %45, %46, %47, %48, %49, %50, %51, %52, %53, %54, %55, %56, %57, %58, %59, %60, %61, %62, %63, %64, %65, %66, %67, %68, %69, %70, %71, %72, %73, %74, %75, %76, %77, %78, %79, %80, %81, %82, %83, %84, %85, %86, %87, %88, %89, %90, %91, %92, %93, %94, %95}, %96, %97, p, 1, 1, 0, 1;\n}\n"
        : "+f"(d[0]), "+f"(d[1]), "+f"(d[2]), "+f"(d[3]), "+f"(d[4]), "+f"(d[5]), "+f"(d[6]), "+f"(d[7]),
          "+f"(d[8]), "+f"(d[9]), "+f"(d[10]), "+f"(d[11]), "+f"(d[12]), "+f"(d[13]), "+f"(d[14]), "+f"(d[15]),
          "+f"(d[16]), "+f"(d[17]), "+f"(d[18]), "+f"(d[19]), "+f"(d[20]), "+f"(d[21]), "+f"(d[22]), "+f"(d[23]),
          "+f"(d[24]), "+f"(d[25]), "+f"(d[26]), "+f"(d[27]), "+f"(d[28]), "+f"(d[29]), "+f"(d[30]), "+f"(d[31]),
          "+f"(d[32]), "+f"(d[33]), "+f"(d[34]), "+f"(d[35]), "+f"(d[36]), "+f"(d[37]), "+f"(d[38]), "+f"(d[39]),
          "+f"(d[40]), "+f"(d[41]), "+f"(d[42]), "+f"(d[43]), "+f"(d[44]), "+f"(d[45]), "+f"(d[46]), "+f"(d[47]),
          "+f"(d[48]), "+f"(d[49]), "+f"(d[50]), "+f"(d[51]), "+f"(d[52]), "+f"(d[53]), "+f"(d[54]), "+f"(d[55]),
          "+f"(d[56]), "+f"(d[57]), "+f"(d[58]), "+f"(d[59]), "+f"(d[60]), "+f"(d[61]), "+f"(d[62]), "+f"(d[63]),
          "+f"(d[64]), "+f"(d[65]), "+f"(d[66]), "+f"(d[67]), "+f"(d[68]), "+f"(d[69]), "+f"(d[70]), "+f"(d[71]),
          "+f"(d[72]), "+f"(d[73]), "+f"(d[74]), "+f"(d[75]), "+f"(d[76]), "+f"(d[77]), "+f"(d[78]), "+f"(d[79]),
          "+f"(d[80]), "+f"(d[81]), "+f"(d[82]), "+f"(d[83]), "+f"(d[84]), "+f"(d[85]), "+f"(d[86]), "+f"(d[87]),
          "+f"(d[88]), "+f"(d[89]), "+f"(d[90]), "+f"(d[91]), "+f"(d[92]), "+f"(d[93]), "+f"(d[94]), "+f"(d[95])
        : "l"(da), "l"(db), "r"(acc));
}
__device__ __forceinline__ void wg_g3(float (&d)[40], uint64_t da, uint64_t db, int acc) {
    asm volatile("{\n.reg .pred p;\nsetp.ne.b32 p, %42, 0;\n"
        "wgmma.mma_async.sync.aligned.m64n80k16.f32.bf16.bf16 {%0, %1, %2, %3, %4, %5, %6, %7, %8, %9, %10, %11, %12, %13, %14, %15, %16, %17, %18, %19, %20, %21, %22, %23, %24, %25, %26, %27, %28, %29, %30, %31, %32, %33, %34, %35, %36, %37, %38, %39}, %40, %41, p, 1, 1, 1, 0;\n}\n"
        : "+f"(d[0]), "+f"(d[1]), "+f"(d[2]), "+f"(d[3]), "+f"(d[4]), "+f"(d[5]), "+f"(d[6]), "+f"(d[7]),
          "+f"(d[8]), "+f"(d[9]), "+f"(d[10]), "+f"(d[11]), "+f"(d[12]), "+f"(d[13]), "+f"(d[14]), "+f"(d[15]),
          "+f"(d[16]), "+f"(d[17]), "+f"(d[18]), "+f"(d[19]), "+f"(d[20]), "+f"(d[21]), "+f"(d[22]), "+f"(d[23]),
          "+f"(d[24]), "+f"(d[25]), "+f"(d[26]), "+f"(d[27]), "+f"(d[28]), "+f"(d[29]), "+f"(d[30]), "+f"(d[31]),
          "+f"(d[32]), "+f"(d[33]), "+f"(d[34]), "+f"(d[35]), "+f"(d[36]), "+f"(d[37]), "+f"(d[38]), "+f"(d[39])
        : "l"(da), "l"(db), "r"(acc));
}
__device__ __forceinline__ void wg_g3t(float (&d)[40], uint64_t da, uint64_t db, int acc) {
    asm volatile("{\n.reg .pred p;\nsetp.ne.b32 p, %42, 0;\n"
        "wgmma.mma_async.sync.aligned.m64n80k16.f32.bf16.bf16 {%0, %1, %2, %3, %4, %5, %6, %7, %8, %9, %10, %11, %12, %13, %14, %15, %16, %17, %18, %19, %20, %21, %22, %23, %24, %25, %26, %27, %28, %29, %30, %31, %32, %33, %34, %35, %36, %37, %38, %39}, %40, %41, p, 1, 1, 1, 1;\n}\n"
        : "+f"(d[0]), "+f"(d[1]), "+f"(d[2]), "+f"(d[3]), "+f"(d[4]), "+f"(d[5]), "+f"(d[6]), "+f"(d[7]),
          "+f"(d[8]), "+f"(d[9]), "+f"(d[10]), "+f"(d[11]), "+f"(d[12]), "+f"(d[13]), "+f"(d[14]), "+f"(d[15]),
          "+f"(d[16]), "+f"(d[17]), "+f"(d[18]), "+f"(d[19]), "+f"(d[20]), "+f"(d[21]), "+f"(d[22]), "+f"(d[23]),
          "+f"(d[24]), "+f"(d[25]), "+f"(d[26]), "+f"(d[27]), "+f"(d[28]), "+f"(d[29]), "+f"(d[30]), "+f"(d[31]),
          "+f"(d[32]), "+f"(d[33]), "+f"(d[34]), "+f"(d[35]), "+f"(d[36]), "+f"(d[37]), "+f"(d[38]), "+f"(d[39])
        : "l"(da), "l"(db), "r"(acc));
}


__device__ __forceinline__ int warp_id() { uint32_t t; asm volatile("mov.u32 %0, %%tid.x;" : "=r"(t)); return __shfl_sync(0xffffffffu, t >> 5, 0); }
__device__ __forceinline__ int lane_id() { uint32_t t; asm volatile("mov.u32 %0, %%laneid;" : "=r"(t)); return t; }
__device__ __forceinline__ void bar_arrive(int id, int n) { asm volatile("bar.arrive %0, %1;" :: "r"(id), "r"(n) : "memory"); }
__device__ __forceinline__ void bar_sync(int id, int n) { asm volatile("bar.sync %0, %1;" :: "r"(id), "r"(n) : "memory"); }
__device__ __forceinline__ void flag_signal(int id) {
    asm volatile("red.release.gpu.global.add.u32 [%0], 1;" :: "l"(g_cnt + id * 32) : "memory");
}
__device__ __forceinline__ void flag_wait(int id, unsigned target) {
    const unsigned* c = g_cnt + id * 32;
    unsigned v; int n = 0;
    do {
        asm volatile("ld.relaxed.gpu.global.u32 %0, [%1];" : "=r"(v) : "l"(c) : "memory");
        if (++n > 400000) __trap();
    } while ((int)(v - target) < 0);
    asm volatile("fence.acquire.gpu;\nfence.proxy.async.global;" ::: "memory");
}
__device__ __forceinline__ void mma16816(float (&c)[4], uint32_t a0, uint32_t a1, uint32_t a2, uint32_t a3, uint32_t b0, uint32_t b1) {
    asm volatile("mma.sync.aligned.m16n8k16.row.col.f32.bf16.bf16.f32 {%0,%1,%2,%3}, {%4,%5,%6,%7}, {%8,%9}, {%0,%1,%2,%3};"
        : "+f"(c[0]), "+f"(c[1]), "+f"(c[2]), "+f"(c[3]) : "r"(a0), "r"(a1), "r"(a2), "r"(a3), "r"(b0), "r"(b1));
}
__device__ __forceinline__ void mma16816h(float (&c)[4], uint32_t a0, uint32_t a1, uint32_t a2, uint32_t a3, uint32_t b0, uint32_t b1) {
    asm volatile("mma.sync.aligned.m16n8k16.row.col.f32.f16.f16.f32 {%0,%1,%2,%3}, {%4,%5,%6,%7}, {%8,%9}, {%0,%1,%2,%3};"
        : "+f"(c[0]), "+f"(c[1]), "+f"(c[2]), "+f"(c[3]) : "r"(a0), "r"(a1), "r"(a2), "r"(a3), "r"(b0), "r"(b1));
}
__device__ __forceinline__ void mma1688h(float (&c)[4], uint32_t a0, uint32_t a1, uint32_t b0) {
    asm volatile("mma.sync.aligned.m16n8k8.row.col.f32.f16.f16.f32 {%0,%1,%2,%3}, {%4,%5}, {%6}, {%0,%1,%2,%3};"
        : "+f"(c[0]), "+f"(c[1]), "+f"(c[2]), "+f"(c[3]) : "r"(a0), "r"(a1), "r"(b0));
}
__device__ __forceinline__ uint32_t movm(uint32_t a) { uint32_t d; asm volatile("movmatrix.sync.aligned.m8n8.trans.b16 %0, %1;" : "=r"(d) : "r"(a)); return d; }
__device__ __forceinline__ float rcp(float x) { float r; asm("rcp.approx.ftz.f32 %0, %1;" : "=f"(r) : "f"(x)); return r; }

constexpr unsigned NCTA = 128;
constexpr int G1_STAGES = 5, G1_X = 0, G1_W = 9 * 16384;
constexpr int G1_ST = G1_W + 40960;
constexpr int AT_Q = 0, AT_KV = 24576, AT_BLK = 12288, AT_TOP = 225280;
constexpr int G3_STAGES = 7, G3_ST = 28672, G3_RING = 24576, G3_OUT = 0;
constexpr int SM_BIAS = G1_W + G1_STAGES * 16384, SM_BAR = SM_BIAS + 2048, SM_TOTAL = SM_BAR + 1024;
constexpr int B_XFULL = 0, B_WFULL = 72, B_WEMPTY = 112, B_XFREE = 152, B_QFULL = 192, B_KVFULL = 208, B_ARDY = 264, B_TOP = 272,
              B_PART = 280, B_G3FULL = 296, B_G3EMPTY = 352, B_BRDY = 408, B_KMAX = 416, B_STFREE = 432, B_QFULL2 = 440, B_TOP2 = 448, B_KVFREE = 480, B_TGT = 608;
constexpr int RC = 144, RH = 80;
constexpr int XEARLY = 6;
constexpr int NPRE = 3;
constexpr int U0 = 21, U1 = 21;

template<int I0, int N, int R>
__device__ __forceinline__ void g1_pack(const float (&acc)[2 * R], uint32_t (&pk)[R], float sc, bool half) {
    if (half) {
        #pragma unroll
        for (int i = I0; i < I0 + N; i++) pk[i] = pack_f16(acc[2 * i] * sc, acc[2 * i + 1] * sc);
    } else {
        #pragma unroll
        for (int i = I0; i < I0 + N; i++) pk[i] = pack_bf16(acc[2 * i], acc[2 * i + 1]);
    }
}
template<int B0, int NB, int R>
__device__ __forceinline__ void g1_store(const uint32_t (&pk)[R], uint8_t* base) {
    #pragma unroll
    for (int b = B0; b < B0 + NB; b++) { stg32(base + (size_t)(b & 7) * CB, pk[2 * b]); stg32(base + (size_t)(b & 7) * CB + 128, pk[2 * b + 1]); }
}

template<int B0, int NB>
__device__ __forceinline__ void g1_store24(const uint32_t (&pk)[48], uint8_t* base) {
    #pragma unroll
    for (int b = B0; b < B0 + NB; b++) { stg32(base + (size_t)b * CB, pk[2 * b]); stg32(base + (size_t)b * CB + 128, pk[2 * b + 1]); }
}
template<int J, int B0, int NB>
__device__ __forceinline__ void g1_store_v(const uint32_t (&pk)[48], uint8_t* base, int t) {
    #pragma unroll
    for (int b = B0; b < B0 + NB; b++) {
        const int v = 24 * J + b, bb = v % 9, c = 12 * (v / 9) + bb + (bb > 0 ? (bb - 1) / 2 : 0);
        if (bb == 2 || bb == 4 || bb == 6) {
            const bool lo = t < bb / 2;
            const uint32_t f0 = bb == 2 && t == 1 ? 0x3f80u : 0u, f1 = t == 0 ? 0x3f80u : 0u;
            stg32(base + (size_t)c * CB, lo ? pk[2 * b] : f0);
            stg32(base + (size_t)c * CB + 128, lo ? pk[2 * b + 1] : f0);
            stg32(base + (size_t)(c + 1) * CB, !lo ? pk[2 * b] : f1);
            stg32(base + (size_t)(c + 1) * CB + 128, !lo ? pk[2 * b + 1] : f1);
        } else {
            stg32(base + (size_t)c * CB, pk[2 * b]);
            stg32(base + (size_t)c * CB + 128, pk[2 * b + 1]);
        }
    }
}

__device__ __forceinline__ void exp_quad(uint32_t* p, const uint32_t* d) {
    uint32_t L[4], R[4];
    #pragma unroll
    for (int i = 0; i < 4; i++) { R[i] = (d[i] << 2) + 0xBEF7BEF7u; asm volatile("" : "+r"(R[i])); }
    #pragma unroll
    for (int i = 0; i < 4; i++) { L[i] = 0xFE78FE78u - R[i]; asm volatile("" : "+r"(L[i])); }
    #pragma unroll
    for (int i = 0; i < 4; i++) asm volatile("fma.rn.bf16x2 %0, %1, %0, %2;" : "+r"(R[i]) : "r"(L[i]), "r"(0x3efb3efbu));
    #pragma unroll
    for (int i = 0; i < 4; i++) asm volatile("fma.rn.bf16x2 %0, %1, %2, %1;" : "=r"(p[i]) : "r"(L[i]), "r"(R[i]));
}
__device__ __forceinline__ void addlo(uint64_t& d, uint32_t v) {
    asm("{\n.reg .b32 lo, hi;\nmov.b64 {lo, hi}, %0;\nadd.u32 lo, lo, %1;\nmov.b64 %0, {lo, hi};\n}" : "+l"(d) : "r"(v));
}
template<int C0, int C1, int N>
__device__ __forceinline__ void at_exp(const uint32_t (&sc)[32], uint32_t (&p)[N]) {
    #pragma unroll
    for (int c = C1 - 1; c >= C0; c--) exp_quad(&p[4 * c], &sc[4 * c]);
}
template<int C0, int C1, int N>
__device__ __forceinline__ void at_pv(const uint32_t (&p)[N], float (&o)[12], uint64_t dv) {
    #pragma unroll
    for (int c = C1 - 1; c >= C0; c--) wg_pv(o, p[4 * c], p[4 * c + 1], p[4 * c + 2], p[4 * c + 3], dv + 16 * c);
}
enum { BLK_MID, BLK_FIRST, BLK_LAST, BLK_LAST_QK };
template<int MODE, class F>
__device__ __forceinline__ void at_block(uint32_t (&sc)[32], uint32_t (&sn)[32], uint32_t (&pc)[8], uint32_t (&pp)[8], float (&o)[12],
                                         const uint32_t (&q)[8], uint64_t dk, uint64_t dk2, uint64_t dvp, uint64_t dvc, F&& pre) {
    wg_fence();
    if (MODE < BLK_LAST) wg_qk0(sn, q[0], q[1], q[2], q[3], dk);
    if (MODE != BLK_FIRST) at_pv<0, 2>(pp, o, dvp);
    if (MODE < BLK_LAST) wg_qk1(sn, q[4], q[5], q[6], q[7], dk2);
    pre();
    at_exp<2, 8>(sc, sc);
    wg_fence();
    if (MODE == BLK_LAST_QK) wg_qk0(sn, q[0], q[1], q[2], q[3], dk);
    if (MODE == BLK_FIRST) { wg_pv0(o, sc[28], sc[29], sc[30], sc[31], dvc + 112); at_pv<2, 7>(sc, o, dvc); }
    else at_pv<2, 8>(sc, o, dvc);
    if (MODE == BLK_LAST_QK) wg_qk1(sn, q[4], q[5], q[6], q[7], dk2);
    if (MODE < BLK_LAST) wg_commit();
    at_exp<0, 2>(sc, pc);
    fence_regs(pc);
    if (MODE >= BLK_LAST) {
        wg_fence();
        at_pv<0, 2>(pc, o, dvc);
        wg_commit();
    }
    wg_wait<0>();
    if (MODE != BLK_LAST) fence_regs(sn);
    if (MODE != BLK_FIRST) fence_regs(pp);
    if (MODE >= BLK_LAST) { fence_regs(pc); fence_regs(o); }
    fence_regs(sc);
}
__device__ __forceinline__ void stg32_if(void* p, uint32_t v, uint32_t c) {
    asm volatile("{\n.reg .pred p;\nsetp.ne.u32 p, %2, 0;\n@p st.global.u32 [%0], %1;\n}" :: "l"(p), "r"(v), "r"(c) : "memory");
}
__device__ __forceinline__ void at_store_o(const float (&o)[12], float s0, float s1, uint8_t* op, uint32_t w0, uint32_t w1, uint32_t w2) {
    stg32_if(op, pack_bf16(o[0] * s0, o[1] * s0), w0); stg32_if(op + 128, pack_bf16(o[2] * s1, o[3] * s1), w0);
    stg32_if(op + CB, pack_bf16(o[4] * s0, o[5] * s0), w1); stg32_if(op + CB + 128, pack_bf16(o[6] * s1, o[7] * s1), w1);
    stg32_if(op + 2 * CB, pack_bf16(o[8] * s0, o[9] * s0), w2); stg32_if(op + 2 * CB + 128, pack_bf16(o[10] * s1, o[11] * s1), w2);
}

__device__ __forceinline__ void at_slow(int h, uint32_t qa, uint8_t* op, int lane) {
    const int r = lane >> 2, t = lane & 3, hi = h & 3, cb0 = 9 * (h >> 2) + 2 * hi;
    const uint8_t* kp = g_scr + (size_t)(CB_KA + cb0) * CB + r * 16 + 4 * t;
    const uint8_t* vp = g_scr + (size_t)(CB_VA + 3 * h) * CB + r * 16 + 4 * t;
    uint32_t q[6];
    #pragma unroll
    for (int c = 0; c < 3; c++) { q[2 * c] = lds32(qa + c * 1024); q[2 * c + 1] = lds32(qa + c * 1024 + 128); }
    if (t < hi) q[0] = q[1] = 0;
    if (t > hi) q[4] = q[5] = 0;
    float o[3][4], m0 = -INFINITY, m1 = -INFINITY;
    #pragma unroll
    for (int i = 0; i < 12; i++) o[i >> 2][i & 3] = 0.f;
    #pragma unroll 1
    for (int kb = 0; kb < 32; kb++) {
        uint32_t k[8][3], v[8][3];
        #pragma unroll
        for (int i = 0; i < 24; i++) { k[i / 3][i % 3] = ldg32(kp + (i % 3) * CB + (i / 3) * 128); v[i / 3][i % 3] = ldg32(vp + (i % 3) * CB + (i / 3) * 128); }
        kp += 1024; vp += 1024;
        float s[8][4], n0 = m0, n1 = m1;
        #pragma unroll
        for (int nb = 0; nb < 8; nb++) {
            s[nb][0] = s[nb][1] = s[nb][2] = s[nb][3] = 0.f;
            mma16816h(s[nb], q[0], q[1], q[2], q[3], k[nb][0], k[nb][1]);
            mma1688h(s[nb], q[4], q[5], k[nb][2]);
            #pragma unroll
            for (int i = 0; i < 4; i++) s[nb][i] *= -524288.f;
            n0 = fmaxf(n0, fmaxf(s[nb][0], s[nb][1])); n1 = fmaxf(n1, fmaxf(s[nb][2], s[nb][3]));
        }
        n0 = fmaxf(n0, __shfl_xor_sync(0xffffffffu, n0, 1)); n1 = fmaxf(n1, __shfl_xor_sync(0xffffffffu, n1, 1));
        n0 = fmaxf(n0, __shfl_xor_sync(0xffffffffu, n0, 2)); n1 = fmaxf(n1, __shfl_xor_sync(0xffffffffu, n1, 2));
        const float f0 = ex2(m0 - n0), f1 = ex2(m1 - n1);
        m0 = n0; m1 = n1;
        #pragma unroll
        for (int c = 0; c < 3; c++) { o[c][0] *= f0; o[c][1] *= f0; o[c][2] *= f1; o[c][3] *= f1; }
        #pragma unroll
        for (int nb = 0; nb < 8; nb += 2) {
            const uint32_t p0 = pack_bf16(ex2(s[nb][0] - m0), ex2(s[nb][1] - m0)), p1 = pack_bf16(ex2(s[nb][2] - m1), ex2(s[nb][3] - m1));
            const uint32_t p2 = pack_bf16(ex2(s[nb + 1][0] - m0), ex2(s[nb + 1][1] - m0)), p3 = pack_bf16(ex2(s[nb + 1][2] - m1), ex2(s[nb + 1][3] - m1));
            #pragma unroll
            for (int c = 0; c < 3; c++) mma16816(o[c], p0, p1, p2, p3, movm(v[nb][c]), movm(v[nb + 1][c]));
        }
    }
    const int src = (lane & ~3) + (hi == 0 ? 1 : 0);
    const float l0 = __shfl_sync(0xffffffffu, hi == 0 ? o[2][0] : o[0][0], src), l1 = __shfl_sync(0xffffffffu, hi == 0 ? o[2][2] : o[0][2], src);
    float of[12];
    #pragma unroll
    for (int i = 0; i < 12; i++) of[i] = o[i >> 2][i & 3];
    at_store_o(of, rcp(l0), rcp(l1), op, t >= hi, 1, t <= hi);
}

struct Span { uint2 q[2][3], k[3][3], v[3][3]; };
__device__ __forceinline__ uint2 ldg64(const void* p) {
    uint2 v; asm volatile("ld.global.v2.u32 {%0,%1}, [%2];" : "=r"(v.x), "=r"(v.y) : "l"(p) : "memory"); return v;
}
__device__ __forceinline__ uint32_t span_off(int sp) {
    const int h = blockIdx.x >> 2;
    return (CB_B + 9 * (h >> 2) + 2 * (h & 3)) * CB + ((blockIdx.x & 3) * 512 + sp * 32) * 16;
}
__device__ __forceinline__ void span_load(Span& S, int sp) {
    const int lane = lane_id();
    const uint8_t* p = g_scr + (span_off(sp) + lane * 8);
    const uint8_t* pv = g_scr + (span_off(sp) + 144 * CB + (lane & 2) * 64 + (lane >> 2) * 16 + (lane & 1) * 8);
    #pragma unroll
    for (int i = 0; i < 9; i++) {
        if (i < 6) S.q[i / 3][i % 3] = ldg64(p + (i % 3) * CB + (i / 3) * 256);
        S.k[i / 3][i % 3] = ldg64(p + (72 + i % 3) * CB + (i / 3 - 1) * 256);
    }
    #pragma unroll
    for (int i = 0; i < 9; i++) S.v[i / 3][i % 3] = ldg64(pv + (i % 3) * CB + (i / 3 - 1) * 256);
}
__device__ __forceinline__ void span_run(Span& S, int sp) {
    const int lane = lane_id(), hi = (blockIdx.x >> 2) & 3, r = lane >> 2, t = lane & 3;
    const bool first = (blockIdx.x & 3) + sp == 0, odd = t & 2;
    const int w = 2 * (t & 1);
    const bool lo0 = 2 * t > r, lo1 = 2 * t + 1 > r;
    const uint32_t mk = (lo0 ? 0xffffu : 0u) | (lo1 ? 0xffff0000u : 0u);
    float a[2][2][2], m[2][2];
    #pragma unroll
    for (int g = 0; g < 2; g++) {
        if (w < hi) S.q[g][0].x = 0;
        if (w + 1 < hi) S.q[g][0].y = 0;
        if (w > hi) S.q[g][2].x = 0;
        if (w + 1 > hi) S.q[g][2].y = 0;
        float s[2][4];
        #pragma unroll
        for (int i = 0; i < 8; i++) s[i >> 2][i & 3] = 0.f;
        #pragma unroll
        for (int c = 0; c < 3; c++) {
            const uint32_t a0 = odd ? 0u : S.q[g][c].x, a1 = odd ? S.q[g][c].x : 0u, a2 = odd ? 0u : S.q[g][c].y, a3 = odd ? S.q[g][c].y : 0u;
            mma16816(s[0], a0, a1, a2, a3, S.k[g][c].x, S.k[g][c].y);
            mma16816(s[1], a0, a1, a2, a3, S.k[g + 1][c].x, S.k[g + 1][c].y);
        }
        if (g == 0 && first) s[0][0] = s[0][1] = s[0][2] = s[0][3] = -INFINITY;
        #pragma unroll
        for (int e = 0; e < 2; e++) {
            a[g][e][0] = lo0 ? s[0][2 * e] : s[1][2 * e]; a[g][e][1] = lo1 ? s[0][2 * e + 1] : s[1][2 * e + 1];
            m[g][e] = fmaxf(a[g][e][0], a[g][e][1]);
        }
    }
    #pragma unroll
    for (int o = 1; o < 4; o *= 2)
        #pragma unroll
        for (int i = 0; i < 4; i++) m[i >> 1][i & 1] = fmaxf(m[i >> 1][i & 1], __shfl_xor_sync(0xffffffffu, m[i >> 1][i & 1], o));
    uint32_t v[2][3][3];
    #pragma unroll
    for (int i = 0; i < 9; i++) {
        v[0][i / 3][i % 3] = __byte_perm(S.v[i / 3][i % 3].x, S.v[i / 3][i % 3].y, 0x5410);
        v[1][i / 3][i % 3] = __byte_perm(S.v[i / 3][i % 3].x, S.v[i / 3][i % 3].y, 0x7632);
    }
    uint8_t* op = g_scr + (span_off(sp) + (CB_OB - CB_B) * CB + (t >> 1) * 128 + r * 16 + (t & 1) * 8);
    const bool w0 = r >= 2 * hi, w2 = r < 2 * hi + 2;
    #pragma unroll
    for (int g = 0; g < 2; g++) {
        float d[2][2][4];
        #pragma unroll
        for (int e = 0; e < 2; e++) {
            const uint32_t pp = pack_bf16(ex2((a[g][e][0] - m[g][e]) * QSCALE), ex2((a[g][e][1] - m[g][e]) * QSCALE));
            #pragma unroll
            for (int i = 0; i < 8; i++) d[e][i >> 2][i & 3] = 0.f;
            mma16816(d[e][0], v[e][g][0], v[e][g][1], v[e][g + 1][0], v[e][g + 1][1], pp & mk, pp & ~mk);
            mma16816(d[e][1], v[e][g][2], 0x3f803f80u, v[e][g + 1][2], 0x3f803f80u, pp & mk, pp & ~mk);
        }
        const float f00 = rcp(d[0][1][2]), f01 = rcp(d[0][1][3]), f10 = rcp(d[1][1][2]), f11 = rcp(d[1][1][3]);
        #pragma unroll
        for (int c = 0; c < 3; c++) {
            const int u = c >> 1, x = (c & 1) * 2;
            const uint32_t o0 = pack_bf16(d[0][u][x] * f00, d[1][u][x] * f10), o1 = pack_bf16(d[0][u][x + 1] * f01, d[1][u][x + 1] * f11);
            asm volatile("{\n.reg .pred p;\nsetp.ne.u32 p, %3, 0;\n@p st.global.v2.u32 [%0], {%1, %2};\n}"
                :: "l"(op + c * CB + g * 256), "r"(o0), "r"(o1), "r"((uint32_t)(c == 0 ? w0 : c == 2 ? w2 : true)) : "memory");
        }
    }
}

struct Params {
    CUtensorMap mx, mwa, mwb, mscr, mq, mst, mo, moa, mob;
    const __nv_bfloat16 *x, *gw, *wa, *wb, *woa, *wob;
    __nv_bfloat16* out;
};

template<int J, int I0>
__device__ __forceinline__ void key_norms(const uint32_t (&pk)[48], uint32_t (&n)[4], int t) {
    constexpr int H0 = (J == 0 ? 0 : J == 1 ? 10 : 21) + I0;
    #pragma unroll
    for (int i = 0; i < 4; i++) {
        uint32_t u[2] = {0, 0};
        #pragma unroll
        for (int c = 0; c < 3; c++) {
            const int h = H0 + i, hi = h & 3, b = 9 * (h >> 2) + 2 * hi + c - 24 * J;
            if (b >= 0 && b < 24) {
                const uint32_t on = c == 0 ? t >= hi : c == 2 ? t <= hi : 1;
                #pragma unroll
                for (int rr = 0; rr < 2; rr++)
                    asm("{\n.reg .pred p;\nsetp.ne.u32 p, %2, 0;\n@p fma.rn.f16x2 %0, %1, %1, %0;\n}" : "+r"(u[rr]) : "r"(pk[2 * b + rr]), "r"(on));
            }
        }
        asm("add.rn.f16x2 %0, %1, %2;" : "=r"(n[i]) : "r"(__byte_perm(u[0], u[1], 0x5410)), "r"(__byte_perm(u[0], u[1], 0x7632)));
    }
}
template<int V> struct Int { static constexpr int value = V; };
__device__ __forceinline__ int g1_atom(int pass, int j, int s) {
    if (pass == 0) return j < 6 ? 9 + 3 * j + s : 3 * (j - 6) + s;
    if (pass == 1) return s == 1 ? 32 + j : (j >= 5 ? 1 + j : 27 + j);
    return 40 + 2 * j + s;
}
__device__ __forceinline__ void phase1_mma(uint32_t sb) {
    const int wid = warp_id(), wg = wid >> 2, warp = wid & 3, lane = lane_id();
    const int tb = blockIdx.x >> 3, j = blockIdx.x & 7;
    const uint32_t bar = sb + SM_BAR;
    const int r = lane >> 2, t = lane & 3;
    const uint64_t da0 = mkdesc(sb + G1_X + wg * 8192, 16, 1024, 1);
    const uint64_t db3 = mkdesc(sb + G1_W, 4096, 1024, 1), db2 = mkdesc(sb + G1_W, 8192, 1024, 1);
    int slot = 0, ph = 0;
    #define G1_NEXT(S) \
        wg_wait<1>(); \
        if ((S) != 0 && lane == 0) mbar_arrive(bar + B_WEMPTY + 8 * (slot == 0 ? G1_STAGES - 1 : slot - 1)); \
        if (++slot == G1_STAGES) { slot = 0; ph ^= 1; }
    #define G1_STAGE2(ACC, S, SIDE) { \
        mbar_wait(bar + B_WFULL + 8 * slot, ph); \
        const uint64_t da = da0 + (S) * 1024, db = db2 + slot * 1024; \
        wg_fence(); \
        wg_g1h(ACC, da, db, (S) != 0); wg_g1h(ACC, da + 2, db + 128, 1); wg_g1h(ACC, da + 4, db + 256, 1); wg_g1h(ACC, da + 6, db + 384, 1); \
        wg_commit(); \
        SIDE \
        G1_NEXT(S) }
    #define G1_DRAIN(ACC) \
        wg_wait<0>(); \
        fence_regs(ACC); \
        if (lane == 0) mbar_arrive(bar + B_WEMPTY + 8 * (slot == 0 ? G1_STAGES - 1 : slot - 1));
    uint8_t* const rowp = g_scr + (size_t)(tb * 128 + wg * 64 + warp * 16 + r) * 16 + 4 * t;
    uint32_t pk[48];
    {
        float acc[96];
        #pragma unroll 1
        for (int s = 0; s < 18; s++) {
            if (!(s & 1)) mbar_wait(bar + B_XFULL + 4 * s, 0);
            mbar_wait(bar + B_WFULL + 8 * slot, ph);
            const uint64_t da = da0 + (s >> 1) * 1024 + (s & 1) * 4, db = db3 + slot * 1024;
            wg_fence();
            wg_g1b(acc, da, db, s != 0);
            wg_g1b(acc, da + 2, db + 128, 1);
            wg_commit();
            G1_NEXT(s)
        }
        G1_DRAIN(acc)
        g1_pack<0, 48>(acc, pk, j < 3 ? KA_SCALE : QA_SCALE, j < 3 || j >= 6);
        fence_regs(pk);
    }
    uint32_t pb[32];
    {
        float acc[64];
        uint32_t n[4] = {0, 0, 0, 0};
        uint8_t* const ap = rowp + (size_t)(j < 3 ? CB_KA + 24 * j : j < 6 ? CB_VA : CB_QA + 24 * (j - 6)) * CB;
        uint16_t* const np = g_kn + ((j == 0 ? 0 : j == 1 ? 11 : 23) + t) * SEQ + (tb * 64 + wid * 8 + r) * 2;
        auto side = [&](auto sc) {
            constexpr int s = decltype(sc)::value;
            if (j >= 3 && j < 6) {
                if constexpr (s < 8) { if (j == 3) g1_store_v<0, 3 * s, 3>(pk, ap, t); else if (j == 4) g1_store_v<1, 3 * s, 3>(pk, ap, t); else g1_store_v<2, 3 * s, 3>(pk, ap, t); }
                return;
            }
            if constexpr (s < 8) g1_store24<3 * s, 3>(pk, ap);
            if (j >= 3) return;
            if constexpr (s % 3 == 1) {
                if (j == 0) key_norms<0, 4 * (s / 3)>(pk, n, t); else if (j == 1) key_norms<1, 4 * (s / 3)>(pk, n, t); else key_norms<2, 4 * (s / 3)>(pk, n, t);
            }
            if constexpr (s % 3 == 2) {
                #pragma unroll
                for (int i = 0; i < 2; i++) {
                    const uint32_t o = __shfl_xor_sync(0xffffffffu, (t & 2) ? n[i] : n[2 + i], 2);
                    asm("add.rn.f16x2 %0, %1, %2;" : "=r"(n[i]) : "r"((t & 2) ? n[2 + i] : n[i]), "r"(o));
                }
                const uint32_t o = __shfl_xor_sync(0xffffffffu, (t & 1) ? n[0] : n[1], 1);
                asm("add.rn.f16x2 %0, %1, %2;" : "=r"(n[0]) : "r"((t & 1) ? n[1] : n[0]), "r"(o));
                if (s < 8 || t < 3 || j == 1) stg32(np + 4 * (s / 3) * SEQ, n[0]);
            }
        };
        #define G1_P2(S) G1_STAGE2(acc, S, side(Int<S>());)
        G1_P2(0) G1_P2(1) G1_P2(2) G1_P2(3) G1_P2(4) G1_P2(5) G1_P2(6) G1_P2(7) G1_P2(8)
        #undef G1_P2
        G1_DRAIN(acc)
        g1_pack<0, 16>(acc, pb, QA_SCALE, j >= 5);
        g1_pack<16, 16>(acc, pb, 1.f, false);
        fence_regs(pb);
    }
    uint8_t* const b0p = rowp + (size_t)(j >= 5 ? 8 * (1 + j) : CB_B + 8 * j) * CB;
    uint8_t* const b1p = rowp + (size_t)(CB_B + 8 * (5 + j)) * CB;
    if (j < 7) {
        float acc[64];
        G1_STAGE2(acc, 0, if (j >= 5) (g1_store<0, 8>(pb, b0p)); bar_arrive(1, 288);)
        G1_STAGE2(acc, 1, )
        G1_STAGE2(acc, 2, if (j < 5) (g1_store<0, 4>(pb, b0p));)
        G1_STAGE2(acc, 3, if (j < 5) (g1_store<4, 4>(pb, b0p));) if (lane == 0) mbar_arrive(bar + B_XFREE);
        G1_STAGE2(acc, 4, (g1_store<8, 2>(pb, b1p));)
        G1_STAGE2(acc, 5, (g1_store<10, 2>(pb, b1p));) if (lane == 0) mbar_arrive(bar + B_XFREE + 8);
        G1_STAGE2(acc, 6, (g1_store<12, 2>(pb, b1p));) if (lane == 0) mbar_arrive(bar + B_XFREE + 16);
        G1_STAGE2(acc, 7, (g1_store<14, 2>(pb, b1p));)
        G1_STAGE2(acc, 8, ) if (lane == 0) mbar_arrive(bar + B_XFREE + 24);
        wg_wait<0>();
        fence_regs(acc);
        if (lane == 0) mbar_arrive(bar + B_XFREE + 32);
        g1_pack<0, 32>(acc, pb, 1.f, false);
        mbar_wait(bar + B_XFREE + 24, 0);
        const uint32_t la = sb + G1_ST + (lane >> 4) * 2048 + (wg * 64 + warp * 16 + (lane & 15)) * 16;
        #pragma unroll
        for (int b = 0; b < 16; b += 2) {
            if (13 + 2 * j + (b >> 3) < 18)
                asm volatile("stmatrix.sync.aligned.m8n8.x4.shared.b16 [%0], {%1, %2, %3, %4};" :: "r"(la + b * 2048),
                    "r"(pb[2 * b]), "r"(pb[2 * b + 1]), "r"(pb[2 * b + 2]), "r"(pb[2 * b + 3]) : "memory");
            else
                asm volatile("stmatrix.sync.aligned.m8n8.x4.trans.shared.b16 [%0], {%1, %2, %3, %4};" :: "r"(la + b * 2048),
                    "r"(pb[2 * b]), "r"(pb[2 * b + 1]), "r"(pb[2 * b + 2]), "r"(pb[2 * b + 3]) : "memory");
        }
        asm volatile("fence.proxy.async.shared::cta;" ::: "memory");
    } else {
        g1_store<0, 8>(pb, b0p);
        bar_arrive(1, 288);
        if (lane == 0) {
            #pragma unroll
            for (int i = 0; i < 5; i++) mbar_arrive(bar + B_XFREE + 8 * i);
        }
        g1_store<8, 8>(pb, b1p);
    }
    bar_arrive(2, 288);
}

__device__ __forceinline__ float norm2(const uint4 c0, const uint4 c1, const uint4 c2, int hi) {
    uint32_t u = 0, w = 0;
    #define SQA(acc, v) { uint32_t x; asm("mul.rn.f16x2 %0, %1, %2;" : "=r"(x) : "r"(v), "r"(0x64006400u)); asm("fma.rn.f16x2 %0, %1, %1, %0;" : "+r"(acc) : "r"(x)); }
    SQA(u, c1.x) SQA(w, c1.y) SQA(u, c1.z) SQA(w, c1.w) SQA(u, c0.w) SQA(w, c2.x)
    SQA(u, hi < 1 ? c0.x : c2.y) SQA(w, hi < 2 ? c0.y : c2.z) SQA(u, hi < 3 ? c0.z : c2.w)
    #undef SQA
    const float2 a = __half22float2(*(const __half2*)&u), b = __half22float2(*(const __half2*)&w);
    return (a.x + a.y) + (b.x + b.y);
}
__device__ __forceinline__ void tops2(uint32_t sb, int i, float k2, int half) {
    #pragma unroll
    for (int u = 0; u < 2; u++) {
        const int tl = ((half ? 0x5421 : 0x7630) >> (8 * u + 4 * (i >> 6))) & 15;
        const uint32_t a = sb + AT_Q + tl * 3072 + (i & 63) * 16;
        const float q2 = norm2(lds128(a), lds128(a + 1024), lds128(a + 2048), (blockIdx.x >> 2) & 3) + 1e-6f;
        float top;
        asm("sqrt.approx.f32 %0, %1;" : "=f"(top) : "f"(q2 * k2));
        top = top * (512.f * 1.006f) + 0.25f;
        sts32(sb + AT_TOP + tl * 256 + (i & 63) * 4, top <= 120.f ? (uint32_t)__half_as_ushort(__float2half_ru(top * (1.f / 512.f))) : 0x10000u);
    }
}
__device__ __forceinline__ float kmax2(uint32_t bar) {
    const uint4 km = lds128(bar + B_KMAX);
    return __half2float(__ushort_as_half((unsigned short)max(max(km.x, km.y), max(km.z, km.w)))) + 1e-6f;
}
__device__ __forceinline__ void row_tops(uint32_t sb, int i) {
    const int h = blockIdx.x >> 2;
    const uint32_t bar = sb + SM_BAR;
    mbar_wait(bar + B_ARDY, 0);
    const uint4* p = (const uint4*)(g_kn + (h + (h > 10) + (h > 21)) * SEQ) + i;
    uint4 a[2] = {__ldcg(p), __ldcg(p + 128)};
    if (h == 10 || h == 21) {
        #pragma unroll
        for (int u = 0; u < 2; u++) {
            const uint4 b = __ldcg(p + 256 + 128 * u);
            asm("add.rn.f16x2 %0, %0, %1;" : "+r"(a[u].x) : "r"(b.x)); asm("add.rn.f16x2 %0, %0, %1;" : "+r"(a[u].y) : "r"(b.y));
            asm("add.rn.f16x2 %0, %0, %1;" : "+r"(a[u].z) : "r"(b.z)); asm("add.rn.f16x2 %0, %0, %1;" : "+r"(a[u].w) : "r"(b.w));
        }
    }
    uint32_t m = __vmaxu2(__vmaxu2(__vmaxu2(a[0].x, a[0].y), __vmaxu2(a[0].z, a[0].w)), __vmaxu2(__vmaxu2(a[1].x, a[1].y), __vmaxu2(a[1].z, a[1].w)));
    m = __reduce_max_sync(0xffffffffu, max(m & 0xffffu, m >> 16));
    sts32(bar + B_KMAX + 4 * (i >> 5), m);
    bar_sync(8, 128);
    const float k2 = kmax2(bar);
    mbar_wait(bar + B_XFREE + 24, 0);
    mbar_wait(bar + B_QFULL, 0);
    tops2(sb, i, k2, 0);
    __syncwarp();
    if ((i & 31) == 0) mbar_arrive(bar + B_TOP);
}

__device__ __forceinline__ void phase2_attn(uint32_t sb) {
    const int wid = warp_id(), wg = wid >> 2, warp = wid & 3, lane = lane_id();
    const int h = blockIdx.x >> 2, qq = blockIdx.x & 3, hi = h & 3;
    const int cb0 = 9 * (h >> 2) + 2 * hi;
    const uint32_t bar = sb + SM_BAR;
    const int r = lane >> 2, t = lane & 3;
    constexpr int F1 = 24 - U0, F2 = 48 - U0 - U1;
    static_assert(F1 >= 2 && F1 <= 6 && F2 >= 2 && F2 <= 6, "split");
    const int nun = wg == 0 ? U0 : wg == 1 ? U1 : 64 - U0 - U1;
    uint32_t seq = wg == 0 ? 0x8210 : wg == 1 ? 0x85423 : 0x8756;
    const int gtile = wg == 0 ? 8 : wg == 1 ? 2 : 5, tile1 = wg == 0 ? 2 : wg == 1 ? 5 : 7;
    const uint32_t qa = __shfl_sync(0xffffffffu, sb + AT_Q + (warp * 16 + r) * 16 + 4 * t, lane);
    const uint32_t m0 = __shfl_sync(0xffffffffu, t >= hi ? ~0u : 0u, lane), m2 = __shfl_sync(0xffffffffu, t <= hi ? ~0u : 0u, lane);
    const uint32_t ooff = __shfl_sync(0xffffffffu, (CB_QA + cb0) * CB + (qq * 512 + warp * 16 + r) * 16 + 4 * t, lane);
    const int src = __shfl_sync(0xffffffffu, (lane & ~3) + (hi == 0 ? 1 : 0), lane);
    const uint64_t dk0 = mkdesc(sb + AT_KV, 2048, 128, 0), dk20 = mkdesc(sb + AT_KV + 4096, SM_BIAS - AT_KV - 4096, 128, 0),
                   dv0 = mkdesc(sb + AT_KV + 6144, 128, 2048, 0);
    constexpr uint32_t S1 = AT_BLK / 16, S2 = S1 - (S1 << 16);
    constexpr uint64_t L1 = S1, L2 = L1 - (L1 << 16);
    uint32_t q[8], bad = 0;
    int fa = (int)(bar + B_KVFREE) - 8 * (nun - 7);
    const int fthr = __shfl_sync(0xffffffffu, lane == 0 ? (int)(bar + B_KVFREE) : 0x7fffffff, lane);
    uint32_t kvb = bar + B_KVFULL + 8;
    static_assert(((SM_BAR + B_KVFULL) & 15) == 0, "parity");
    mbar_wait(bar + B_TOP, 0);
    mbar_wait(bar + B_KVFULL, 0);
    float o[12] = {1.f, 1.f, 1.f, 1.f, 1.f, 1.f, 1.f, 1.f, 1.f, 1.f, 1.f, 1.f};
    uint32_t s0[32], s1[32], p0[8], p1[8];
    auto load_q = [&](int tile) {
        const uint32_t a = qa + tile * 3072, ta = sb + AT_TOP + tile * 256 + ((qa >> 2) & 0xfc);
        q[0] = lds32(a) & m0; q[1] = lds32(a + 128) & m0; q[2] = lds32(a + 1024); q[3] = lds32(a + 1024 + 128);
        q[4] = lds32(a + 2048) & m2; q[5] = lds32(a + 2048 + 128) & m2;
        q[6] = lds32(ta); q[7] = lds32(ta + 32);
        if ((q[6] | q[7]) >> 16) bad |= 1u << tile;
        fence_regs(q);
    };
    auto finish = [&](int tile, uint32_t on) {
        const float l0 = __shfl_sync(0xffffffffu, hi == 0 ? o[8] : o[0], src), l1 = __shfl_sync(0xffffffffu, hi == 0 ? o[10] : o[2], src);
        at_store_o(o, rcp(l0), rcp(l1), g_scr + (ooff + tile * 1024), m0 & on, on, m2 & on);
        if (!(fminf(l0, l1) >= 1.43e-14f)) bad |= on << tile;
    };
    auto nop = [] {};
    const int lb0 = wg == 0 ? F1 : wg == 1 ? F2 : 0;
    uint64_t dk = dk0, dk2 = dk20, dv = dv0;
    int nu = 8, ptile = gtile;
    bool first = true;
    load_q(seq & 15);
    wg_fence();
    wg_qk0(s0, q[0], q[1], q[2], q[3], dk);
    wg_qk1(s0, q[4], q[5], q[6], q[7], dk2);
    wg_commit();
    wg_wait<0>();
    fence_regs(s0);
    #pragma unroll 1
    while (true) {
        const int tile = seq & 15;
        seq >>= 4;
        at_block<BLK_FIRST>(s0, s1, p0, p1, o, q, dk + L1, dk2 + L2, dv, dv, [&] { finish(ptile, ptile != gtile); });
        const int fend = fa + 8 * (nu - 1);
        int e = fend;
        if (first) { mbar_wait(kvb, 0); kvb += 8; e = fa + 16; }
        addlo(dk, 2 * S1); addlo(dk2, 2 * S2);
        #pragma unroll 1
        while (true) {
            if (fa >= fthr) mbar_arrive(fa);
            fa += 8;
            at_block<BLK_MID>(s1, s0, p1, p0, o, q, dk, dk2, dv, dv + L1, nop);
            at_block<BLK_MID>(s0, s1, p0, p1, o, q, dk + L1, dk2 + L2, dv + L1, dv + 2 * L1, nop);
            addlo(dk, 2 * S1); addlo(dk2, 2 * S2); addlo(dv, 2 * S1);
            if (__builtin_expect(fa < e, 1)) continue;
            if (fa >= fend) break;
            mbar_wait(kvb, 0);
            kvb += 8;
            e += 16 + (kvb & 8);
        }
        fence_regs(s1); fence_regs(p0); fence_regs(o);
        if (fa >= fthr) mbar_arrive(fa);
        fa += 8;
        if (tile == tile1) break;
        const int nt = seq & 15, b0 = nt == tile1 ? lb0 : 0;
        const uint64_t dvl = dv;
        nu = nt == gtile ? (wg == 1 ? F1 : F2) : 8 - b0;
        ptile = tile;
        dk = dk0; dk2 = dk20; dv = dv0;
        addlo(dk, b0 * 2 * S1); addlo(dk2, b0 * 2 * S2); addlo(dv, b0 * 2 * S1);
        if (first) {
            Span S;
            mbar_wait(bar + B_TOP2, 0);
            at_block<BLK_LAST>(s1, s0, p1, p0, o, q, 0, 0, dvl, dvl + L1, [&] { span_load(S, 4 + wid); });
            bar_arrive(11, 512);
            load_q(nt);
            span_run(S, 4 + wid);
            wg_fence();
            wg_qk0(s0, q[0], q[1], q[2], q[3], dk);
            wg_qk1(s0, q[4], q[5], q[6], q[7], dk2);
            wg_commit();
            bar_sync(3, 512);
            wg_wait<0>();
            fence_regs(s0);
            first = false;
            continue;
        }
        at_block<BLK_LAST_QK>(s1, s0, p1, p0, o, q, dk, dk2, dvl, dvl + L1, [&] { load_q(nt); });
        if (tile == gtile) {
            float4* part = g_part + (blockIdx.x * 2 + wg - 1) * 384 + (threadIdx.x & 127);
            #pragma unroll
            for (int i = 0; i < 3; i++) part[i * 128] = make_float4(o[4 * i], o[4 * i + 1], o[4 * i + 2], o[4 * i + 3]);
            __syncwarp();
            if (fthr != 0x7fffffff) mbar_arrive(bar + B_PART + 8 * (wg - 1));
            __syncwarp();
        }
    }
    {
        float4 v[3];
        #pragma unroll
        for (int i = 0; i < 3; i++) v[i] = make_float4(0.f, 0.f, 0.f, 0.f);
        if (wg != 2) {
            mbar_wait(bar + B_PART + 8 * wg, 0);
            #pragma unroll
            for (int i = 0; i < 3; i++) v[i] = __ldcg(g_part + (blockIdx.x * 2 + wg) * 384 + (threadIdx.x & 127) + i * 128);
        }
        at_block<BLK_LAST>(s1, s0, p1, p0, o, q, 0, 0, dv, dv + L1, nop);
        #pragma unroll
        for (int i = 0; i < 3; i++) { o[4 * i] += v[i].x; o[4 * i + 1] += v[i].y; o[4 * i + 2] += v[i].z; o[4 * i + 3] += v[i].w; }
        finish(tile1, 1);
    }
    if (fa >= fthr) mbar_arrive(fa);
    bad = __reduce_or_sync(0xffffffffu, bad & ~(1u << gtile));
    #pragma unroll 1
    while (bad) {
        const int tl = __ffs(bad) - 1;
        bad &= bad - 1;
        at_slow(h, qa + tl * 3072, g_scr + (ooff + tl * 1024), lane_id());
    }
    bar_arrive(4, 416);
}

__device__ __forceinline__ void phase3_mma(const Params& P, uint32_t sb) {
    const int wid = warp_id(), wg = wid >> 2, warp = wid & 3, lane = lane_id();
    const int ti = blockIdx.x / 9, fa = blockIdx.x - 9 * ti, tok0 = min(160 * ti, SEQ - 160);
    const uint32_t bar = sb + SM_BAR;
    float accb[40], acca[40];
    const uint64_t da0 = mkdesc(sb + G3_RING, 8192, 1024, 1), db0 = mkdesc(sb + G3_RING + 8192 + wg * 10240, 1280, 128, 0);
    int slot = 0, ph = 0;
    #define G3_STAGE(MMA, ACC, G) { \
        mbar_wait(bar + B_G3FULL + 8 * slot, ph); \
        wg_fence(); \
        _Pragma("unroll") \
        for (int kk = 0; kk < 4; kk++) MMA(ACC, da0 + slot * (G3_ST / 16) + kk * 128, db0 + slot * (G3_ST / 16) + kk * 160, (G) != 0 || kk != 0); \
        wg_commit(); \
        wg_wait<1>(); \
        if ((G) != 0 && lane == 0) mbar_arrive(bar + B_G3EMPTY + 8 * (slot == 0 ? G3_STAGES - 1 : slot - 1)); \
        if (++slot == G3_STAGES) { slot = 0; ph ^= 1; } }
    #pragma unroll 1
    for (int g = 0; g < 9; g++) G3_STAGE(wg_g3t, accb, g);
    wg_wait<0>();
    fence_regs(accb);
    if (lane == 0) mbar_arrive(bar + B_G3EMPTY + 8);
    float2 gt[10];
    #pragma unroll
    for (int b = 0; b < 10; b++) gt[b] = __ldcg((const float2*)(g_gate + tok0 + wg * 80 + 8 * b + 2 * (lane & 3)));
    #pragma unroll
    for (int b = 0; b < 10; b++) {
        const float h0 = rbf(1.f - gt[b].x), h1 = rbf(1.f - gt[b].y);
        accb[4 * b] *= h0; accb[4 * b + 1] *= h1; accb[4 * b + 2] *= h0; accb[4 * b + 3] *= h1;
    }
    fence_regs(accb);
    #pragma unroll 1
    for (int g = 0; g < 9; g++) { G3_STAGE(wg_g3, acca, g); }
    wg_wait<0>();
    fence_regs(acca);
    const uint32_t st = sb + G3_OUT + wg * 10240;
    const uint32_t la = st + ((lane >> 4) * 8 + (lane & 7)) * 128 + (((2 * warp + ((lane >> 3) & 1)) ^ (lane & 7)) << 4);
    uint32_t pk[20];
    #pragma unroll
    for (int b = 0; b < 10; b++) {
        const float g0 = gt[b].x, g1 = gt[b].y;
        pk[2 * b] = pack_bf16(fmaf(g0, acca[4 * b], accb[4 * b]), fmaf(g1, acca[4 * b + 1], accb[4 * b + 1]));
        pk[2 * b + 1] = pack_bf16(fmaf(g0, acca[4 * b + 2], accb[4 * b + 2]), fmaf(g1, acca[4 * b + 3], accb[4 * b + 3]));
    }
    #pragma unroll
    for (int b = 0; b < 10; b += 2)
        asm volatile("stmatrix.sync.aligned.m8n8.x4.trans.shared.b16 [%0], {%1, %2, %3, %4};" :: "r"(la + b * 1024),
            "r"(pk[2 * b]), "r"(pk[2 * b + 1]), "r"(pk[2 * b + 2]), "r"(pk[2 * b + 3]) : "memory");
    bar_sync(5 + wg, 128);
    {
        const int row = warp * 4 + (lane >> 3), ch = lane & 7;
        uint4* op = (uint4*)(P.out + (size_t)(tok0 + wg * 80 + row) * DM + fa * 64) + ch;
        const uint32_t a = st + row * 128 + ((ch ^ (row & 7)) << 4);
        uint4 v[5];
        #pragma unroll
        for (int i = 0; i < 5; i++) v[i] = lds128(a + i * 2048);
        #pragma unroll
        for (int i = 0; i < 5; i++) op[i * 16 * (DM / 8)] = v[i];
    }
}

__global__ void __launch_bounds__(512, 1) fused_kernel(const __grid_constant__ Params P) {
    extern __shared__ __align__(1024) uint8_t smem[];
    const uint32_t sb = uniform(s2u(smem));
    const uint32_t bar = sb + SM_BAR;
    const int tid = threadIdx.x, wid = uniform(tid >> 5), wg = wid >> 2, warp = wid & 3, lane = tid & 31;
    if (wid == 12) {
        if (elect_one()) {
            const int tb = blockIdx.x >> 3, c1 = g1_atom(0, blockIdx.x & 7, 0) * 64;
            #pragma unroll
            for (int g = 0; g < G1_STAGES; g++) {
                if (g == 0) { mbar_init(bar + B_XFULL, 1); mbar_init(bar + B_WFULL, 1); }
                if (g == 1) {
                    #pragma unroll
                    for (int i = 1; i < 9; i++) { mbar_init(bar + B_XFULL + 8 * i, 1); if (i < 5) mbar_init(bar + B_WFULL + 8 * i, 1); }
                }
                if (g < 2) asm volatile("fence.mbarrier_init.release.cluster;" ::: "memory");
                if (!(g & 1)) {
                    mbar_expect(bar + B_XFULL + 4 * g, 16384);
                    tma2d(sb + G1_X + g * 8192, &P.mx, g * 32, tb * 128, bar + B_XFULL + 4 * g);
                }
                mbar_expect(bar + B_WFULL + 8 * g, 12288);
                #pragma unroll
                for (int a = 0; a < 3; a++) tma2d(sb + G1_W + g * 16384 + a * 4096, &P.mwa, c1 + a * 64, g * 32, bar + B_WFULL + 8 * g);
            }
            #pragma unroll
            for (int xi = 3; xi < XEARLY; xi++) {
                mbar_expect(bar + B_XFULL + 8 * xi, 16384);
                tma2d(sb + G1_X + xi * 16384, &P.mx, xi * 64, tb * 128, bar + B_XFULL + 8 * xi);
            }
        }
    } else if (wg == 3 && elect_one()) {
        if (warp == 1) {
            #pragma unroll
            for (int i = 0; i < 5; i++) { mbar_init(bar + B_WEMPTY + 8 * i, 8); mbar_init(bar + B_XFREE + 8 * i, 8); }
            mbar_init(bar + B_PART, 4); mbar_init(bar + B_PART + 8, 4);
            mbar_init(bar + B_QFULL, 1); mbar_init(bar + B_BRDY, 1); mbar_init(bar + B_TOP, 4); mbar_init(bar + B_STFREE, 1); mbar_init(bar + B_ARDY, 1);
            mbar_init(bar + B_QFULL2, 1); mbar_init(bar + B_TOP2, 4);
        } else if (warp == 2) {
            #pragma unroll
            for (int i = 0; i < 8; i++) { mbar_init(bar + B_KVFREE + 8 * i, 12); if (i < 4) mbar_init(bar + B_KVFULL + 8 * i, 1); }
        } else {
            #pragma unroll
            for (int i = 0; i < 7; i++) { mbar_init(bar + B_G3FULL + 8 * i, 1); mbar_init(bar + B_G3EMPTY + 8 * i, 8); }
        }
        asm volatile("fence.mbarrier_init.release.cluster;" ::: "memory");
    }
    if (wg == 2) {
        const int i = tid & 127;
        *(uint4*)(smem + SM_BIAS + i * 16) = make_uint4(0x1400u, 0, 0, 0);
        asm volatile("fence.proxy.async.shared::cta;" ::: "memory");
    }
    __syncthreads();
    if (wg == 3) {
        reg_dec<RH>();
        if (warp == 0) {
            if (elect_one()) {
                const int tb = blockIdx.x >> 3, j = blockIdx.x & 7;
                int slot = 0, ph = 0;
                const int c1 = g1_atom(0, j, 0) * 64;
                #pragma unroll 1
                for (int g = G1_STAGES; g < 18; g++) {
                    mbar_wait(bar + B_WEMPTY + 8 * slot, ph);
                    mbar_expect(bar + B_WFULL + 8 * slot, 12288);
                    #pragma unroll
                    for (int a = 0; a < 3; a++) tma2d(sb + G1_W + slot * 16384 + a * 4096, &P.mwa, c1 + a * 64, g * 32, bar + B_WFULL + 8 * slot);
                    const int xi = XEARLY + g - G1_STAGES;
                    if (xi < 9) {
                        mbar_expect(bar + B_XFULL + 8 * xi, 16384);
                        tma2d(sb + G1_X + xi * 16384, &P.mx, xi * 64, tb * 128, bar + B_XFULL + 8 * xi);
                    }
                    if (++slot == G1_STAGES) { slot = 0; ph ^= 1; }
                }
                #pragma unroll 1
                for (int g = 0; g < (j < 7 ? 18 : 9); g++) {
                    const int ps = g < 9 ? 1 : 2, a0 = g1_atom(ps, j, 0), a1 = g1_atom(ps, j, 1), k0 = (g < 9 ? g : g - 9) * 64;
                    const CUtensorMap* m0 = a0 < 27 ? &P.mwa : &P.mwb;
                    const int c0 = (a0 < 27 ? a0 : a0 - 27) * 64;
                    const uint32_t st = sb + G1_W + slot * 16384, fb = bar + B_WFULL + 8 * slot;
                    mbar_wait(bar + B_WEMPTY + 8 * slot, ph);
                    mbar_expect(fb, 16384);
                    tma2d(st, m0, c0, k0, fb);
                    tma2d(st + 4096, m0, c0, k0 + 32, fb);
                    tma2d(st + 8192, &P.mwb, (a1 - 27) * 64, k0, fb);
                    tma2d(st + 12288, &P.mwb, (a1 - 27) * 64, k0 + 32, fb);
                    if (++slot == G1_STAGES) { slot = 0; ph ^= 1; }
                }
            }
        } else if (warp == 1) {
            bar_sync(7, 64);
            bar_sync(1, 288); if (lane == 0) { flag_signal(0); }
            __syncwarp();
            bar_sync(2, 288);
            if (elect_one()) {
                const int j = blockIdx.x & 7;
                if (j < 7) {
                    mbar_wait(bar + B_KVFULL + 8, 0);
                    #pragma unroll
                    for (int a = 0; a < 2; a++)
                        asm volatile("cp.async.bulk.tensor.2d.global.shared::cta.bulk_group [%0, {%2, %3}], [%1];"
                            :: "l"(&P.mst), "r"(sb + G1_ST + a * 16384), "r"((int)(blockIdx.x >> 3) * 256), "r"(CB_B + 8 * (13 + 2 * j + a)) : "memory");
                    asm volatile("cp.async.bulk.commit_group;" ::: "memory");
                    asm volatile("cp.async.bulk.wait_group.read 0;" ::: "memory");
                }
                mbar_arrive(bar + B_STFREE);
                asm volatile("cp.async.bulk.wait_group 0;" ::: "memory");
                flag_signal(1);
            }
        } else if (warp == 2) {
            const unsigned e1 = uniform(*(volatile unsigned*)g_cnt / NCTA + 1);
            sts32(bar + B_TGT, e1);
            bar_arrive(7, 64);
            if (elect_one()) {
                const int h = blockIdx.x >> 2, qq = blockIdx.x & 3, cb0 = 9 * (h >> 2) + 2 * (h & 3);
                flag_wait(0, e1 * NCTA);
                mbar_arrive(bar + B_ARDY);
                mbar_wait(bar + B_XFREE, 0);
                mbar_expect(bar + B_QFULL, 12288);
                #pragma unroll
                for (int u = 0; u < 4; u++) { const int tl = (0x7630 >> (4 * u)) & 15; tma2d(sb + AT_Q + tl * 3072, &P.mq, (qq * 8 + tl) * 128, CB_QA + cb0, bar + B_QFULL); }
                #pragma unroll 1
                for (int i = 0; i < 8; i++) {
                    if (i >= 1 && i <= 4) mbar_wait(bar + B_XFREE + 8 * i, 0);
                    if (i == 6) mbar_wait(bar + B_STFREE, 0);
                    const uint32_t st = sb + AT_KV + 2 * i * AT_BLK, fb = bar + B_KVFULL + 8 * (i == 0 ? 0 : i / 3 + 1);
                    if (i < 2 || i == 3 || i == 6) mbar_expect(fb, (i == 0 ? 2 : i == 3 ? 6 : 4) * AT_BLK);
                    tma2d(st, &P.mscr, i * 512, CB_KA + cb0, fb);
                    tma2d(st + AT_BLK, &P.mscr, i * 512 + 256, CB_KA + cb0, fb);
                    tma2d(st + 6144, &P.mscr, i * 512, CB_VA + 3 * h, fb);
                    tma2d(st + AT_BLK + 6144, &P.mscr, i * 512 + 256, CB_VA + 3 * h, fb);
                    if (i == 5) {
                        mbar_expect(bar + B_QFULL2, 12288);
                        #pragma unroll
                        for (int u = 0; u < 4; u++) { const int tl = (0x5421 >> (4 * u)) & 15; tma2d(sb + AT_Q + tl * 3072, &P.mq, (qq * 8 + tl) * 128, CB_QA + cb0, bar + B_QFULL2); }
                    }
                }
                flag_wait(1, e1 * 128);
                mbar_arrive(bar + B_BRDY);
            }
        } else {
            if (elect_one()) {
                #pragma unroll
                for (int i = 0; i < 7; i++) asm volatile("prefetch.tensormap [%0];" :: "l"(&P.mwb + i) : "memory");
                asm volatile("cp.async.bulk.prefetch.L2.global [%0], %1;" :: "l"((const uint8_t*)P.wa + 160 * 3456 + blockIdx.x * 11232), "r"(11232) : "memory");
                mbar_wait(bar + B_XFULL + 16, 0);
                asm volatile("cp.async.bulk.prefetch.L2.global [%0], %1;" :: "l"((const uint8_t*)P.wb + blockIdx.x * 15552), "r"(15552) : "memory");
                asm volatile("cp.async.bulk.prefetch.L2.global [%0], %1;" :: "l"((const uint8_t*)P.woa + blockIdx.x * 5184), "r"(5184) : "memory");
                asm volatile("cp.async.bulk.prefetch.L2.global [%0], %1;" :: "l"((const uint8_t*)P.wob + blockIdx.x * 5184), "r"(5184) : "memory");
            }
        }
        __syncwarp();
        mbar_wait(bar + B_TOP, 0);
        mbar_wait(bar + B_QFULL2, 0);
        tops2(sb, threadIdx.x & 127, kmax2(bar), 1);
        mbar_wait(bar + B_BRDY, 0);
        __syncwarp();
        if (elect_one()) mbar_arrive(bar + B_TOP2);
        __syncwarp();
        {
            Span S;
            span_load(S, warp_id() & 3);
            bar_sync(11, 512);
            span_run(S, warp_id() & 3);
        }
        const int wid2 = warp_id();
        if (wid2 == 13) {
            bar_sync(3, 512); if (elect_one()) { flag_signal(2); }
            __syncwarp();

            bar_sync(4, 416); if (elect_one()) { flag_signal(3); }
        } else {
            bar_arrive(3, 512);
            if (wid2 == 14)
            if (blockIdx.x < 117 && elect_one()) {
                const int ti = blockIdx.x / 9, fa = blockIdx.x - 9 * ti, tok0 = min(160 * ti, SEQ - 160);
                const unsigned target = lds32(bar + B_TGT) * 128;
                flag_wait(2, target);
                int slot = 0;
                #pragma unroll 1
                for (int g = 0; g < 18; g++) {
                    if (g == 9 + NPRE) {
                        flag_wait(3, target);
                        #pragma unroll 1
                        for (int u = 0; u < NPRE; u++) {
                            const int sl = u < 5 ? u + 2 : u - 5;
                            const uint32_t st = sb + G3_RING + sl * G3_ST, fb = bar + B_G3FULL + 8 * sl;
                            tma2d(st + 8192, &P.mo, tok0 * 2, u * 8, fb);
                            tma2d(st + 8192 + 10240, &P.mo, tok0 * 2 + 160, u * 8, fb);
                        }
                    }
                    if (g < 7) mbar_wait(bar + B_KVFREE + 8 * (g + 1), 0);
                    else mbar_wait(bar + B_G3EMPTY + 8 * slot, g < 14 ? 0 : 1);
                    const uint32_t st = sb + G3_RING + slot * G3_ST, fb = bar + B_G3FULL + 8 * slot;
                    const int kt = g < 9 ? g : g - 9;
                    mbar_expect(fb, G3_ST);
                    tma2d(st, g < 9 ? &P.mob : &P.moa, fa * 64, kt * 64, fb);
                    if (g < 9 || g >= 9 + NPRE) {
                        tma2d(st + 8192, &P.mo, tok0 * 2, (g < 9 ? CB_OB : CB_QA) + kt * 8, fb);
                        tma2d(st + 8192 + 10240, &P.mo, tok0 * 2 + 160, (g < 9 ? CB_OB : CB_QA) + kt * 8, fb);
                    }
                    if (++slot == G3_STAGES) slot = 0;
                }
            }
        }
    } else {
        reg_inc<RC>();
        if (wg < 2) phase1_mma(sb);
        else
        {
            uint32_t w[9];
            #pragma unroll
            for (int i = 0; i < 9; i++) w[i] = ((const uint32_t*)P.gw)[lane + 32 * i];
            #pragma unroll 1
            for (int tk = warp; tk < 16; tk += 4) {
                const int tok = blockIdx.x * 16 + tk;
                const uint32_t* xr = (const uint32_t*)(P.x + (size_t)tok * DM);
                float s = 0.f;
                #pragma unroll
                for (int i = 0; i < 9; i++) {
                    const uint32_t v = xr[lane + 32 * i];
                    s += rbf(bf_lo(v) * bf_lo(w[i])) + rbf(bf_hi(v) * bf_hi(w[i]));
                }
                #pragma unroll
                for (int o = 16; o > 0; o >>= 1) s += __shfl_xor_sync(0xffffffffu, s, o);
                s = rbf(s);
                if (lane == 0) g_gate[tok] = rbf(rcp(1.f + ex2(-1.4426950408889634f * s)));
            }
            row_tops(sb, tid & 127);
        }
        phase2_attn(sb);
        if (warp_id() < 8 && blockIdx.x < 117) phase3_mma(P, sb);
    }
}

typedef CUresult (*EncodeFn)(CUtensorMap*, CUtensorMapDataType, cuuint32_t, void*, const cuuint64_t*, const cuuint64_t*,
                             const cuuint32_t*, const cuuint32_t*, CUtensorMapInterleave, CUtensorMapSwizzle,
                             CUtensorMapL2promotion, CUtensorMapFloatOOBfill);
static void enc(EncodeFn fn, CUtensorMap* m, CUtensorMapDataType dt, const void* p, cuuint64_t d0, cuuint64_t d1, cuuint64_t stride,
                cuuint32_t b0, cuuint32_t b1, CUtensorMapSwizzle sw) {
    cuuint64_t d[2] = {d0, d1}, s[1] = {stride};
    cuuint32_t b[2] = {b0, b1}, es[2] = {1, 1};
    fn(m, dt, 2, (void*)p, d, s, b, es, CU_TENSOR_MAP_INTERLEAVE_NONE, sw, CU_TENSOR_MAP_L2_PROMOTION_L2_128B,
       CU_TENSOR_MAP_FLOAT_OOB_FILL_NONE);
}

extern "C" void kernel_launch(void* const* d_in, const int* in_sizes, int n_in, void* d_out, int out_size) {
    static EncodeFn fn = nullptr;
    static uint8_t* scr = nullptr;
    if (!fn) {
        cudaDriverEntryPointQueryResult qr;
        cudaGetDriverEntryPoint("cuTensorMapEncodeTiled", (void**)&fn, cudaEnableDefault, &qr);
        cudaGetSymbolAddress((void**)&scr, g_scr);
        cudaFuncSetAttribute(fused_kernel, cudaFuncAttributeMaxDynamicSharedMemorySize, SM_TOTAL);
    }
    Params P;
    const CUtensorMapDataType BF = CU_TENSOR_MAP_DATA_TYPE_BFLOAT16, U64 = CU_TENSOR_MAP_DATA_TYPE_UINT64;
    const CUtensorMapSwizzle SW = CU_TENSOR_MAP_SWIZZLE_128B, NS = CU_TENSOR_MAP_SWIZZLE_NONE;
    enc(fn, &P.mx, BF, d_in[0], 576, 2048, 1152, 64, 128, SW);
    enc(fn, &P.mwa, BF, d_in[1], 1728, 576, 3456, 64, 32, SW);
    enc(fn, &P.mwb, BF, d_in[4], 1728, 576, 3456, 64, 32, SW);
    enc(fn, &P.mscr, U64, scr, 4096, CB_TOTAL, CB, 256, 3, NS);
    enc(fn, &P.mq, U64, scr, 4096, CB_TOTAL, CB, 128, 3, NS);
    enc(fn, &P.mst, U64, scr, 4096, CB_TOTAL, CB, 256, 8, NS);
    enc(fn, &P.mo, U64, scr, 4096, CB_TOTAL, CB, 160, 8, NS);
    enc(fn, &P.moa, BF, d_in[2], 576, 576, 1152, 64, 64, SW);
    enc(fn, &P.mob, BF, d_in[5], 576, 576, 1152, 64, 64, SW);
    P.x = (const __nv_bfloat16*)d_in[0]; P.gw = (const __nv_bfloat16*)d_in[6];
    P.wa = (const __nv_bfloat16*)d_in[1]; P.wb = (const __nv_bfloat16*)d_in[4];
    P.woa = (const __nv_bfloat16*)d_in[2]; P.wob = (const __nv_bfloat16*)d_in[5];
    P.out = (__nv_bfloat16*)d_out;
    fused_kernel<<<NCTA, 512, SM_TOTAL, cudaStreamPerThread>>>(P);
}
```
